```python
import torch

def _softmax(x, axis=-1):
    return torch.softmax(x, dim=axis)
def _gelu(x):
    return torch.nn.functional.gelu(x, approximate="tanh")
def _silu(x):
    return torch.nn.functional.silu(x)
def _sigmoid(x):
    return torch.sigmoid(x)
def _layernorm(x, axis=-1, eps=1e-5):
    m = x.mean(dim=axis, keepdim=True)
    v = x.var(dim=axis, keepdim=True, unbiased=False)
    return (x - m) / torch.sqrt(v + eps)
def _scatter_add(tgt, idx, src, axis=0):
    return tgt.clone().index_add_(axis, idx, src)
def _segment_sum(src, seg, n):
    out = torch.zeros((n,) + src.shape[1:], dtype=src.dtype)
    return out.index_add_(0, seg, src)
def _pad(x, pw):
    flat = tuple(v for pair in reversed(pw) for v in pair)
    return torch.nn.functional.pad(x, flat)

kernel_name = 'standalone__deep_cross_xdeepfm__recsys'

def setup_inputs():

    _w = (lambda a: (lambda t: t.to(torch.bfloat16) if t.is_floating_point() else t)(torch.as_tensor(a)))
    B, F, D, L = 1024, 26, 128, 6
    V = min(1000000, 100000)
    Din = F * D
    return {
        "idx": _w((lambda lo, hi, *s: torch.randint(lo, hi, s))(0, V, B, F).to(torch.int64)),
        "table": _w((lambda *s: torch.randn(*s, dtype=torch.bfloat16) * 0.8)(V, D)),
        "ws_cin": _w((lambda *s: torch.randn(*s, dtype=torch.bfloat16) * 0.1)(L, F, F, F) * (1.0 / F)),
        "w_cin_out": _w((lambda *s: torch.randn(*s, dtype=torch.bfloat16) * 0.1)(L * F) * ((L * F) ** -0.5)),
        "w_dnn1": _w((lambda *s: torch.randn(*s, dtype=torch.bfloat16) * 0.8)(Din, Din) * (Din ** -0.5)),
        "b_dnn1": _w((lambda *s: torch.randn(*s, dtype=torch.bfloat16) * 1.6)(Din) * 0.1),
        "w_dnn2": _w((lambda *s: torch.randn(*s, dtype=torch.bfloat16) * 0.1)(Din) * (Din ** -0.5)),
        "b_out": _w((lambda *s: torch.randn(*s, dtype=torch.bfloat16) * 0.1)(1)),
    }

def reference(idx, table, ws_cin, w_cin_out, w_dnn1, b_dnn1, w_dnn2, b_out):
    x0 = table[idx]
    B = x0.shape[0]
    L = ws_cin.shape[0]
    xk = x0
    pooled = []
    for l in range(L):
        xk = torch.einsum('bid,bjd,hij->bhd', xk, x0, ws_cin[l])
        pooled.append(xk.sum(axis=-1))
    p_plus = torch.stack(pooled, axis=1).reshape(B, -1)
    logit_cin = p_plus @ w_cin_out
    h = x0.reshape(B, -1)
    h = _gelu(h @ w_dnn1 + b_dnn1)
    logit_dnn = h @ w_dnn2
    return logit_cin + logit_dnn + b_out
```

```cpp
#include <cuda_runtime.h>
#include <cuda_bf16.h>
#include <cuda.h>
#include <stdint.h>

namespace {

constexpr int NK1 = 24;
__host__ __device__ constexpr int r_item(int i) {
  constexpr unsigned short t[48] = {413, 532, 281, 484, 429, 325, 480, 724, 372, 157, 152, 206, 485, 360, 465, 277, 280, 885, 412, 460, 149, 464, 498, 492, 348, 137, 481, 533, 500, 669, 156, 349, 404, 341, 493, 436, 276, 817, 452, 153, 405, 409, 453, 725, 424, 668, 448, 148};
  return t[i];
}
__host__ __device__ constexpr int tail_pos(int t) {
  constexpr unsigned char p[7] = {1, 5, 7, 10, 11, 13, 23};
  return p[t];
}
__device__ __align__(16) const unsigned int c_tab[228] = {
    86509032, 111347267, 95159821, 69207585, 100927172, 120588076, 119866725, 118163256,
    107545888, 111281828, 92866028, 96470688, 105383495, 94570125, 94897480, 73467075,
    97060334, 112133711, 107742832, 104859217, 77726884, 90179360, 114361893, 116786966,
    113772231, 92472972, 95094122, 119605030, 96732548, 120522545, 107283616, 118621957,
    121767748, 122357593, 123078469, 123144024, 103286504, 107152835, 105711277, 100730241,
    103745263, 108136014, 105907888, 103810604, 88737593, 69272741, 110364440, 84411887,
    83952865, 113444564, 116197098, 75564228, 117573380, 90769193, 114165189, 116590355,
    107480679, 73533058, 94963017, 96536006, 107086912, 90309988, 113837775, 116262645,
    107939296, 104990276, 101254671, 103679665, 108201811, 75760452, 56231770, 97388366,
    86443495, 112461458, 92931594, 79693350, 120063783, 77792901, 118294282, 98633190,
    102893282, 107677131, 114427605, 116393708, 83887328, 75695748, 99419626, 111216294,
    84084359, 81987208, 94766401, 94438726, 92800391, 102958737, 94373184, 77661381,
    81921252, 109774644, 113902917, 115738374, 103876337, 41092718, 106038962, 101713420,
    101189127, 100861584, 120391466, 90244454, 100796098, 101385611, 120981195, 116066103,
    122160967, 121833300, 122488650, 121702214, 111675144, 117638435, 94832077, 71370337,
    103220967, 110298766, 105514666, 101057926, 84018436, 90375971, 114099621, 115410689,
    86246884, 120915762, 92603909, 117442321, 71435394, 90900267, 114689733, 116852503,
    96994759, 98764431, 107808362, 104924742, 122226511, 123012946, 122423120, 121636689,
    107218048, 119670564, 86312421, 118359829, 73598595, 82248967, 80086209, 95225258,
    90703207, 115541748, 94504258, 109119110, 103352041, 112395950, 105645740, 100664704,
    86115810, 111871563, 114034384, 115344113, 86574569, 112526002, 93061644, 67110432,
    84215013, 73401984, 103613994, 113313478, 96601474, 99288619, 114493120, 116524773,
    118032143, 111740489, 97256974, 106956401, 111609607, 118752905, 88540618, 79824486,
    84280550, 88278666, 94635332, 86050086, 103024356, 120784686, 105186981, 118490892,
    84610310, 169414935, 33821440, 134678799, 17960982, 235672856, 320471828, 1508874,
    17109774, 186188292, 51647762, 369954828, 252778505, 68814600, 285344516, 337121813,
    369428751, 218762256, 386406667, 318768910, 437913089, 370411273, 135204876, 387452437,
    17170449, 67308313, 302318099, 236588298, 656614957, 808596273, 674505002, 941963556,
    926296866, 539768105, 303247150, 0,
};

constexpr int kB = 1024, kF = 26, kD = 128, kDin = kF * kD;
constexpr int kPrepCtas = 28, kGemmCtas = 104, kCtas = kPrepCtas + kGemmCtas;
constexpr int kThreads = 384;
constexpr int kStages = 4, kStageBytes = 49152, kABytes = 16384, kBBytes = 32768;
constexpr int kKSteps = kDin / 64;
constexpr int kTiles = 2 * kB;
#define PREP_TILES 756
constexpr int kTilesPrep = PREP_TILES, kBaseTiles = 12, kHeadLayers = 1;
constexpr int kSplit = kTiles - kTilesPrep - kBaseTiles * kGemmCtas;
constexpr int kPlainRows = kB - kSplit, kPlain = 2 * kPlainRows;
constexpr int kMaxTiles = 32;
static_assert((kTilesPrep + kPrepCtas - 1) / kPrepCtas < kMaxTiles, "per-CTA tile budget");
static_assert(kSplit > 0 && kSplit <= 2 * kPrepCtas && kBaseTiles % 3 == 0, "split tile schedule");
__host__ __device__ constexpr int item_row(int t) {
  return t < kPlain ? t >> 1 : t < kPlain + kSplit ? t - kPlainRows : t < kTiles ? t - kPlainRows - kSplit : kB - 1;
}
__host__ __device__ constexpr int item_half(int t) { return t < kPlain ? t & 1 : t >= kPlain + kSplit; }

constexpr int kS1Step = 56 * 32, kZStep = 32 * 32;
constexpr int kNKZ = 43;
constexpr int kSec0Bytes = NK1 * kS1Step;
constexpr int kSecLBytes = kNKZ * kZStep;
constexpr int kImgBytes = kSec0Bytes + 3 * kSecLBytes;
constexpr int kTabPi = NK1 * 32, kTabLin = kTabPi + 112, kTabBytes = kTabLin + 32;

constexpr int kXPitch = 144, kXBytes = (kF + 1) * kXPitch;
constexpr int kOffX = kStages * kStageBytes;
constexpr int kOffLd = kOffX + 3 * kXBytes;
constexpr int kOffBar = kOffLd + 1024;
constexpr int kOffMisc = kOffBar + 192;
constexpr int kOffTag = kOffMisc + 4, kOffTicket = kOffMisc + 8;
constexpr int kOffPart = kOffMisc + 16;
constexpr int kOffEpi = kOffPart + kMaxTiles * 16;
constexpr int kSmemBytes = kOffEpi + 4096;

constexpr int kBarFull = 0, kBarEmpty = 4, kBarDone = 8, kBarW = 12, kBarFin = 16;
constexpr uint32_t kSpinLimit = 1u << 22;

__device__ __align__(128) unsigned char g_img[kImgBytes];
__device__ unsigned long long g_dnn[13 * kB];
__device__ unsigned long long g_half[kCtas * 4];
__device__ unsigned long long g_pool[kSplit * 4];
__device__ uint4 g_state[kSplit * 12 * 128];
__device__ unsigned int g_ticket;
__device__ unsigned long long g_exit_cnt;
__device__ unsigned int g_prep_cnt;

struct Params {
  const int* idx;
  const unsigned short* table;
  const unsigned short* ws;
  const unsigned short* wout;
  const unsigned short* b1;
  const unsigned short* w2;
  const unsigned short* bout;
  unsigned short* out;
  const unsigned int* tab;
  unsigned char* img;
  unsigned long long* dnn;
  unsigned long long* half;
  unsigned long long* pool;
  uint4* state;
  unsigned int* ticket;
  unsigned long long* exit_cnt;
  unsigned int* prep_cnt;
};

#define LT(i)
#define LTARG
#define LTPARAM
#define TS(i)
template <int OFF, int ACC>
__device__ __forceinline__ void wgmma_rs_n8(float* d, uint32_t a0, uint32_t a1, uint32_t a2, uint32_t a3, uint32_t lo) {
  asm volatile("{\n.reg .b32 t, h;\n.reg .b64 e;\nadd.u32 t, %8, %9;\nmov.b32 h, 16;\nmov.b64 e, {t, h};\n"
    "wgmma.mma_async.sync.aligned.m64n8k16.f32.bf16.bf16 {%0, %1, %2, %3}, {%4, %5, %6, %7}, e, %10, 1, 1, 0;\n}\n"
    : "+f"(d[0]), "+f"(d[1]), "+f"(d[2]), "+f"(d[3])
    : "r"(a0), "r"(a1), "r"(a2), "r"(a3), "r"(lo), "n"(OFF), "n"(ACC));
}
template <int OFF, int ACC>
__device__ __forceinline__ void wgmma_rs_n32(float* d, uint32_t a0, uint32_t a1, uint32_t a2, uint32_t a3, uint32_t lo) {
  asm volatile("{\n.reg .b32 t, h;\n.reg .b64 e;\nadd.u32 t, %20, %21;\nmov.b32 h, 16;\nmov.b64 e, {t, h};\n"
    "wgmma.mma_async.sync.aligned.m64n32k16.f32.bf16.bf16 {%0, %1, %2, %3, %4, %5, %6, %7, %8, %9, %10, %11, %12, %13, %14, %15}, {%16, %17, %18, %19}, e, %22, 1, 1, 0;\n}\n"
    : "+f"(d[0]), "+f"(d[1]), "+f"(d[2]), "+f"(d[3]), "+f"(d[4]), "+f"(d[5]), "+f"(d[6]), "+f"(d[7]), "+f"(d[8]), "+f"(d[9]), "+f"(d[10]), "+f"(d[11]), "+f"(d[12]), "+f"(d[13]), "+f"(d[14]), "+f"(d[15])
    : "r"(a0), "r"(a1), "r"(a2), "r"(a3), "r"(lo), "n"(OFF), "n"(ACC));
}
template <int OFF, int ACC>
__device__ __forceinline__ void wgmma_rs_n56(float* d, uint32_t a0, uint32_t a1, uint32_t a2, uint32_t a3, uint32_t lo) {
  asm volatile("{\n.reg .b32 t, h;\n.reg .b64 e;\nadd.u32 t, %32, %33;\nmov.b32 h, 16;\nmov.b64 e, {t, h};\n"
    "wgmma.mma_async.sync.aligned.m64n56k16.f32.bf16.bf16 {%0, %1, %2, %3, %4, %5, %6, %7, %8, %9, %10, %11, %12, %13, %14, %15, %16, %17, %18, %19, %20, %21, %22, %23, %24, %25, %26, %27}, {%28, %29, %30, %31}, e, %34, 1, 1, 0;\n}\n"
    : "+f"(d[0]), "+f"(d[1]), "+f"(d[2]), "+f"(d[3]), "+f"(d[4]), "+f"(d[5]), "+f"(d[6]), "+f"(d[7]), "+f"(d[8]), "+f"(d[9]), "+f"(d[10]), "+f"(d[11]), "+f"(d[12]), "+f"(d[13]), "+f"(d[14]), "+f"(d[15]), "+f"(d[16]), "+f"(d[17]), "+f"(d[18]), "+f"(d[19]), "+f"(d[20]), "+f"(d[21]), "+f"(d[22]), "+f"(d[23]), "+f"(d[24]), "+f"(d[25]), "+f"(d[26]), "+f"(d[27])
    : "r"(a0), "r"(a1), "r"(a2), "r"(a3), "r"(lo), "n"(OFF), "n"(ACC));
}
__device__ __forceinline__ void wgmma_ss_n256_tb(float* d, uint64_t da, uint64_t db, int sd) {
  asm volatile("{\n.reg .pred p;\nsetp.ne.b32 p, %130, 0;\n"
    "wgmma.mma_async.sync.aligned.m64n256k16.f32.bf16.bf16 {%0, %1, %2, %3, %4, %5, %6, %7, %8, %9, %10, %11, %12, %13, %14, %15, %16, %17, %18, %19, %20, %21, %22, %23, %24, %25, %26, %27, %28, %29, %30, %31, %32, %33, %34, %35, %36, %37, %38, %39, %40, %41, %42, %43, %44, %45, %46, %47, %48, %49, %50, %51, %52, %53, %54, %55, %56, %57, %58, %59, %60, %61, %62, %63, %64, %65, %66, %67, %68, %69, %70, %71, %72, %73, %74, %75, %76, %77, %78, %79, %80, %81, %82, %83, %84, %85, %86, %87, %88, %89, %90, %91, %92, %93, %94, %95, %96, %97, %98, %99, %100, %101, %102, %103, %104, %105, %106, %107, %108, %109, %110, %111, %112, %113, %114, %115, %116, %117, %118, %119, %120, %121, %122, %123, %124, %125, %126, %127}, %128, %129, p, 1, 1, 0, 1;\n}\n"
    : "+f"(d[0]), "+f"(d[1]), "+f"(d[2]), "+f"(d[3]), "+f"(d[4]), "+f"(d[5]), "+f"(d[6]), "+f"(d[7]), "+f"(d[8]), "+f"(d[9]), "+f"(d[10]), "+f"(d[11]), "+f"(d[12]), "+f"(d[13]), "+f"(d[14]), "+f"(d[15]), "+f"(d[16]), "+f"(d[17]), "+f"(d[18]), "+f"(d[19]), "+f"(d[20]), "+f"(d[21]), "+f"(d[22]), "+f"(d[23]), "+f"(d[24]), "+f"(d[25]), "+f"(d[26]), "+f"(d[27]), "+f"(d[28]), "+f"(d[29]), "+f"(d[30]), "+f"(d[31]), "+f"(d[32]), "+f"(d[33]), "+f"(d[34]), "+f"(d[35]), "+f"(d[36]), "+f"(d[37]), "+f"(d[38]), "+f"(d[39]), "+f"(d[40]), "+f"(d[41]), "+f"(d[42]), "+f"(d[43]), "+f"(d[44]), "+f"(d[45]), "+f"(d[46]), "+f"(d[47]), "+f"(d[48]), "+f"(d[49]), "+f"(d[50]), "+f"(d[51]), "+f"(d[52]), "+f"(d[53]), "+f"(d[54]), "+f"(d[55]), "+f"(d[56]), "+f"(d[57]), "+f"(d[58]), "+f"(d[59]), "+f"(d[60]), "+f"(d[61]), "+f"(d[62]), "+f"(d[63]), "+f"(d[64]), "+f"(d[65]), "+f"(d[66]), "+f"(d[67]), "+f"(d[68]), "+f"(d[69]), "+f"(d[70]), "+f"(d[71]), "+f"(d[72]), "+f"(d[73]), "+f"(d[74]), "+f"(d[75]), "+f"(d[76]), "+f"(d[77]), "+f"(d[78]), "+f"(d[79]), "+f"(d[80]), "+f"(d[81]), "+f"(d[82]), "+f"(d[83]), "+f"(d[84]), "+f"(d[85]), "+f"(d[86]), "+f"(d[87]), "+f"(d[88]), "+f"(d[89]), "+f"(d[90]), "+f"(d[91]), "+f"(d[92]), "+f"(d[93]), "+f"(d[94]), "+f"(d[95]), "+f"(d[96]), "+f"(d[97]), "+f"(d[98]), "+f"(d[99]), "+f"(d[100]), "+f"(d[101]), "+f"(d[102]), "+f"(d[103]), "+f"(d[104]), "+f"(d[105]), "+f"(d[106]), "+f"(d[107]), "+f"(d[108]), "+f"(d[109]), "+f"(d[110]), "+f"(d[111]), "+f"(d[112]), "+f"(d[113]), "+f"(d[114]), "+f"(d[115]), "+f"(d[116]), "+f"(d[117]), "+f"(d[118]), "+f"(d[119]), "+f"(d[120]), "+f"(d[121]), "+f"(d[122]), "+f"(d[123]), "+f"(d[124]), "+f"(d[125]), "+f"(d[126]), "+f"(d[127])
    : "l"(da), "l"(db), "r"(sd));
}

__device__ __forceinline__ void wg_fence() { asm volatile("wgmma.fence.sync.aligned;" ::: "memory"); }
__device__ __forceinline__ void wg_commit() { asm volatile("wgmma.commit_group.sync.aligned;" ::: "memory"); }
template <int N> __device__ __forceinline__ void wg_wait() { asm volatile("wgmma.wait_group.sync.aligned %0;" ::"n"(N) : "memory"); }
template <int N> __device__ __forceinline__ void pin(float* r) {
#pragma unroll
  for (int i = 0; i < N; i++) asm volatile("" : "+f"(r[i])::"memory");
}
template <int N> __device__ __forceinline__ void pin(uint32_t* r) {
#pragma unroll
  for (int i = 0; i < N; i++) asm volatile("" : "+r"(r[i])::"memory");
}

__device__ __forceinline__ void mbar_init(uint32_t bar, uint32_t count) {
  asm volatile("mbarrier.init.shared::cta.b64 [%0], %1;" ::"r"(bar), "r"(count) : "memory");
}
__device__ __forceinline__ bool mbar_try(uint32_t bar, uint32_t parity) {
  uint32_t ok;
  asm volatile("{\n.reg .pred p;\nmbarrier.try_wait.parity.shared::cta.b64 p, [%1], %2;\nselp.u32 %0, 1, 0, p;\n}\n"
               : "=r"(ok) : "r"(bar), "r"(parity) : "memory");
  return ok;
}
__device__ __forceinline__ void mbar_wait(uint32_t bar, uint32_t parity) {
  uint32_t spins = 0;
  while (!mbar_try(bar, parity)) {
    if (++spins > kSpinLimit) __trap();
  }
}
__device__ __forceinline__ void mbar_wait_idle(uint32_t bar, uint32_t parity) {
  uint32_t spins = 0, ok;
  do {
    asm volatile("{\n.reg .pred p;\nmbarrier.try_wait.parity.shared::cta.b64 p, [%1], %2, %3;\nselp.u32 %0, 1, 0, p;\n}\n"
                 : "=r"(ok) : "r"(bar), "r"(parity), "r"(10000u) : "memory");
    if (++spins > kSpinLimit) __trap();
  } while (!ok);
}
__device__ __forceinline__ void mbar_arrive(uint32_t bar) {
  asm volatile("mbarrier.arrive.shared::cta.b64 _, [%0];" ::"r"(bar) : "memory");
}
__device__ __forceinline__ void mbar_arrive_cluster(uint32_t bar, uint32_t cta) {
  asm volatile("{\n.reg .b32 ra;\nmapa.shared::cluster.u32 ra, %0, %1;\n"
               "mbarrier.arrive.shared::cluster.b64 _, [ra];\n}\n" ::"r"(bar), "r"(cta) : "memory");
}
__device__ __forceinline__ void mbar_expect_tx(uint32_t bar, uint32_t bytes) {
  asm volatile("mbarrier.arrive.expect_tx.shared::cta.b64 _, [%0], %1;" ::"r"(bar), "r"(bytes) : "memory");
}
__device__ __forceinline__ void bulk_g2s(uint32_t dst, const void* src, uint32_t bytes, uint32_t bar) {
  asm volatile("cp.async.bulk.shared::cluster.global.mbarrier::complete_tx::bytes [%0], [%1], %2, [%3];"
               ::"r"(dst), "l"(src), "r"(bytes), "r"(bar) : "memory");
}
__device__ __forceinline__ void tma_2d_mc(uint32_t dst, const CUtensorMap* map, int c0, int c1, uint32_t bar, uint16_t mask) {
  asm volatile("cp.async.bulk.tensor.2d.shared::cluster.global.mbarrier::complete_tx::bytes.multicast::cluster"
               " [%0], [%1, {%3, %4}], [%2], %5;"
               ::"r"(dst), "l"(map), "r"(bar), "r"(c0), "r"(c1), "h"(mask) : "memory");
}
__device__ __forceinline__ void cp_async16(uint32_t dst, const void* src) {
  asm volatile("cp.async.cg.shared.global [%0], [%1], 16;" ::"r"(dst), "l"(src) : "memory");
}
__device__ __forceinline__ void cp_async16_row(uint32_t dst, const void* src) {
  asm volatile("cp.async.cg.shared.global.L2::256B [%0], [%1], 16;" ::"r"(dst), "l"(src) : "memory");
}
__device__ __forceinline__ void cp_async_arrive(uint32_t bar) {
  asm volatile("cp.async.mbarrier.arrive.noinc.shared::cta.b64 [%0];" ::"r"(bar) : "memory");
}
__device__ __forceinline__ void fence_proxy_async() { asm volatile("fence.proxy.async.global;" ::: "memory"); }
__device__ __forceinline__ void fence_proxy_async_smem() { asm volatile("fence.proxy.async.shared::cta;" ::: "memory"); }
__device__ __forceinline__ void bar_sync(int id, int n) { asm volatile("bar.sync %0, %1;" ::"r"(id), "r"(n) : "memory"); }
__device__ __forceinline__ void wait_prep(const Params& p, uint32_t tag) {
  uint32_t spins = 0, v;
  do {
    asm volatile("ld.acquire.gpu.global.u32 %0, [%1];" : "=r"(v) : "l"(p.prep_cnt) : "memory");
    if (++spins > kSpinLimit) __trap();
  } while ((int)(v - tag * kPrepCtas) < 0);
}
__device__ __forceinline__ unsigned long long ld_relaxed64(const unsigned long long* p) {
  unsigned long long v;
  asm volatile("ld.relaxed.gpu.global.u64 %0, [%1];" : "=l"(v) : "l"(p) : "memory");
  return v;
}
__device__ __forceinline__ void st_tagged(unsigned long long* p, float v, uint32_t tag) {
  asm volatile("st.relaxed.gpu.global.u64 [%0], %1;" ::"l"(p), "l"((unsigned long long)tag << 32 | __float_as_uint(v)) : "memory");
}
__device__ __forceinline__ uint32_t tag_of(unsigned long long exits) { return (uint32_t)(exits / kCtas) + 1; }
__device__ __forceinline__ uint32_t read_launch_tag(const Params& p) { return tag_of(ld_relaxed64(p.exit_cnt)); }
__device__ __forceinline__ uint32_t lds32(uint32_t a) {
  uint32_t r;
  asm volatile("ld.shared.u32 %0, [%1];" : "=r"(r) : "r"(a) : "memory");
  return r;
}
__device__ __forceinline__ void sts32(uint32_t a, uint32_t v) { asm volatile("st.shared.u32 [%0], %1;" ::"r"(a), "r"(v) : "memory"); }
__device__ __forceinline__ void sts128(uint32_t a, uint32_t x, uint32_t y, uint32_t z, uint32_t w) {
  asm volatile("st.shared.v4.u32 [%0], {%1, %2, %3, %4};" ::"r"(a), "r"(x), "r"(y), "r"(z), "r"(w) : "memory");
}
__device__ __forceinline__ uint4 ld_relaxed128(const uint4* p) {
  unsigned long long a, b;
  asm volatile("ld.relaxed.gpu.global.v2.u64 {%0, %1}, [%2];" : "=l"(a), "=l"(b) : "l"(p) : "memory");
  return make_uint4((uint32_t)a, (uint32_t)(a >> 32), (uint32_t)b, (uint32_t)(b >> 32));
}
__device__ __forceinline__ void st_relaxed128(uint4* p, uint32_t x, uint32_t y, uint32_t z, uint32_t w) {
  asm volatile("st.relaxed.gpu.global.v2.u64 [%0], {%1, %2};" ::"l"(p), "l"((unsigned long long)y << 32 | x),
               "l"((unsigned long long)w << 32 | z) : "memory");
}
template <int N>
__device__ __forceinline__ float sum_tagged(const unsigned long long* p, int stride, uint32_t tag) {
  unsigned long long v[N];
  uint32_t spins = 0;
  bool ok;
  do {
    ok = true;
#pragma unroll
    for (int i = 0; i < N; i++) v[i] = ld_relaxed64(p + i * stride);
#pragma unroll
    for (int i = 0; i < N; i++) ok = ok && (uint32_t)(v[i] >> 32) == tag;
    if (++spins > kSpinLimit) __trap();
  } while (!ok);
  float s = 0.f;
#pragma unroll
  for (int i = 0; i < N; i++) s += __uint_as_float((uint32_t)v[i]);
  return s;
}
__device__ __forceinline__ void cluster_arrive() { asm volatile("barrier.cluster.arrive.relaxed.aligned;" ::: "memory"); }
__device__ __forceinline__ void cluster_wait() { asm volatile("barrier.cluster.wait.acquire.aligned;" ::: "memory"); }
__device__ __forceinline__ int ldg_early(const int* p) {
  int v;
  asm volatile("ld.global.nc.b32 %0, [%1];" : "=r"(v) : "l"(p));
  return v;
}
__device__ __forceinline__ const unsigned char* row_address(const unsigned char* base, int row) {
  const unsigned char* a;
  asm volatile("mad.wide.u32 %0, %1, 256, %2;" : "=l"(a) : "r"(row), "l"(base));
  return a;
}
__device__ __forceinline__ bool elect_one() {
  uint32_t r;
  asm volatile("{\n.reg .pred p;\nelect.sync _|p, 0xffffffff;\nselp.u32 %0, 1, 0, p;\n}\n" : "=r"(r));
  return r;
}
__device__ __forceinline__ void bar_arrive(int id, int n) { asm volatile("bar.arrive %0, %1;" ::"r"(id), "r"(n) : "memory"); }
__device__ __forceinline__ float4 lds128f(uint32_t a) {
  float4 r;
  asm volatile("ld.shared.v4.f32 {%0, %1, %2, %3}, [%4];" : "=f"(r.x), "=f"(r.y), "=f"(r.z), "=f"(r.w) : "r"(a) : "memory");
  return r;
}
__device__ __forceinline__ uint4 lds128u(uint32_t a) {
  uint4 r;
  asm volatile("ld.shared.v4.u32 {%0, %1, %2, %3}, [%4];" : "=r"(r.x), "=r"(r.y), "=r"(r.z), "=r"(r.w) : "r"(a));
  return r;
}
__device__ __forceinline__ void ldsm4t(uint32_t* r, uint32_t a) {
  asm volatile("ldmatrix.sync.aligned.m8n8.x4.trans.shared.b16 {%0, %1, %2, %3}, [%4];"
               : "=r"(r[0]), "=r"(r[1]), "=r"(r[2]), "=r"(r[3]) : "r"(a) : "memory");
}
__device__ __forceinline__ uint32_t hmul2(uint32_t a, uint32_t b) {
  uint32_t r;
  asm("mul.rn.bf16x2 %0, %1, %2;" : "=r"(r) : "r"(a), "r"(b));
  return r;
}
__device__ __forceinline__ uint32_t dup_lo(uint32_t a) {
  uint32_t r;
  asm("{.reg .b16 l, h; mov.b32 {l, h}, %1; mov.b32 %0, {l, l};}" : "=r"(r) : "r"(a));
  return r;
}
__device__ __forceinline__ uint32_t dup_hi(uint32_t a) {
  uint32_t r;
  asm("{.reg .b16 l, h; mov.b32 {l, h}, %1; mov.b32 %0, {h, h};}" : "=r"(r) : "r"(a));
  return r;
}
__device__ __forceinline__ uint32_t pack_bf16(float lo, float hi) {
  uint32_t r;
  asm("cvt.rn.bf16x2.f32 %0, %1, %2;" : "=r"(r) : "f"(hi), "f"(lo));
  return r;
}
__device__ __forceinline__ float tanh_fast(float x) {
  float r;
  asm("tanh.approx.f32 %0, %1;" : "=f"(r) : "f"(x));
  return r;
}
__device__ __forceinline__ float bf2f(unsigned short u) { return __uint_as_float((uint32_t)u << 16); }
__device__ __forceinline__ unsigned short f2bf(float f) { return __bfloat16_as_ushort(__float2bfloat16_rn(f)); }

__device__ __forceinline__ uint32_t desc_plain(uint32_t addr) {
  return __shfl_sync(0xffffffffu, ((addr & 0x3FFFF) >> 4) | ((128 >> 4) << 16), 0);
}
__host__ __device__ constexpr int img_off(int step_bytes, int ks, int n, int kk) {
  return ks * step_bytes + (n >> 3) * 256 + (kk >> 3) * 128 + (n & 7) * 16 + (kk & 7) * 2;
}
__host__ __device__ constexpr int own_i(int q, int u) { return 8 * (u >> 1) + 2 * q + (u & 1); }

__device__ __forceinline__ void build_tables(const Params& p, uint32_t sb, int e, bool is_gemm, int n0) {
  uint32_t sym[2];
#pragma unroll
  for (int r = 0; r < 2; r++) {
    const int ln = (e >> 3) + 16 * r, slot = min(2 * (e & 7) + (ln >> 4), 13);
    const int pos = kTabPi + ((ln & 7) >> 1) * 28 + 2 * slot + (ln & 1);
    sym[r] = ((uint32_t)ldg_early(reinterpret_cast<const int*>(p.tab) + (pos >> 2)) >> (8 * (pos & 3))) & 0xff;
  }
  uint4 ww = make_uint4(0, 0, 0, 0);
  if (is_gemm && (e & 7) == 0) ww = __ldg(reinterpret_cast<const uint4*>(p.w2 + n0) + (e >> 3));
  uint4 wx = make_uint4(0, 0, 0, 0);
  if (is_gemm && (e & 7) == 0) wx = __ldg(reinterpret_cast<const uint4*>(p.w2 + n0) + 16 + (e >> 3));
#pragma unroll
  for (int r = 0; r < 2; r++) sts32(sb + kOffLd + (e + 128 * r) * 4, sym[r] * kXPitch + ((e >> 6) & 1) * 16);
  if (e >= 64 && e < 88)
    sts128(sb + kOffX + ((e - 64) >> 3) * kXBytes + kF * kXPitch + (e & 7) * 16, 0x3f803f80u, 0x3f803f80u, 0x3f803f80u, 0x3f803f80u);
  if (is_gemm) {
    sts128(sb + kOffEpi + e * 16, ww.x, ww.y, ww.z, ww.w);
    sts128(sb + kOffEpi + 2048 + e * 16, wx.x, wx.y, wx.z, wx.w);
  }
}

__device__ __forceinline__ void cin_issue(const Params& p, uint32_t dst, int warp, int tile, int row) {
  const unsigned char* src = row_address(reinterpret_cast<const unsigned char*>(p.table) + (warp * 32 + item_half(tile) * 128), row);
  cp_async16(dst, src);
  cp_async16(dst + 16, src + 16);
  asm volatile("cp.async.commit_group;" ::: "memory");
}
__device__ __forceinline__ int cin_row(const Params& p, int tile, int lane) {
  return __ldg(p.idx + (uint32_t)(item_row(tile) * kF) + (uint32_t)min(lane, kF - 1));
}

__device__ __forceinline__ void init_barriers(uint32_t sb) {
  for (int s = 0; s < kStages; s++) {
    mbar_init(sb + kOffBar + (kBarFull + s) * 8, 129);
    mbar_init(sb + kOffBar + (kBarEmpty + s) * 8, 16);
    mbar_init(sb + kOffBar + (kBarDone + s) * 8, 8);
    mbar_init(sb + kOffBar + (kBarW + s) * 8, 1);
  }
  mbar_init(sb + kOffBar + kBarFin * 8, kThreads / 32);
  sts32(sb + kOffMisc, 0);
  asm volatile("fence.mbarrier_init.release.cluster;" ::: "memory");
}

constexpr int kSq = kF * kF, kCube = kSq * kF, kUnit0 = kPrepCtas - 21, kSlice = 1408, kHalf = kThreads / 2;
constexpr int oW6 = 0, oSl = 36864, oTab = oSl + 5 * kSlice, oU = oTab + 1024, oW5 = oU + 2704, oM = oW5 + 2704,
              oC = oM + 2704, oL = oC + 320, oWo = oL + 128;

__device__ __forceinline__ uint32_t prep_issue(const Params& p, uint32_t sb, int cta, int tid) {
  const unsigned char* ws = reinterpret_cast<const unsigned char*>(p.ws);
#pragma unroll
  for (int it = 0; it < 6; it++) {
    const int c = min(tid + it * kThreads, kCube / 8 - 1);
    cp_async16(sb + oW6 + c * 16, ws + 10 * kCube + c * 16);
  }
  const int unit = max(cta - kUnit0, 0), step = unit / 7, part = unit % 7, col = min(cta, kF - 1);
  const uint32_t wpair = (uint32_t)ldg_early(reinterpret_cast<const int*>(
      tid < kSq / 2 ? p.ws + 4 * kCube + ((tid / 13) * kF + col) * kF + 2 * (tid % 13)
                    : p.wout + 3 * kF + 2 * min(tid - kSq / 2, 3 * 13 - 1)));
  const int sl = tid >> 6, c = min(tid & 63, 42);
  const int h = part < 6 ? own_i(sl & 3, part) : 24 + (sl & 1);
  const int off = (2 * (sl < 4 ? (3 - step) * kCube + h * kSq : col * kSq)) & ~15;
  const unsigned char* src = sl < 5 ? ws + off : reinterpret_cast<const unsigned char*>(p.tab);
  const int c2 = min(c + 43, sl < 5 ? 84 : kTabBytes / 16 - 1);
  cp_async16(sb + oSl + sl * kSlice + c * 16, src + c * 16);
  cp_async16(sb + oSl + sl * kSlice + c2 * 16, src + c2 * 16);
  if (tid < 10) cp_async16(sb + oWo + tid * 16, reinterpret_cast<const unsigned char*>(p.wout) + tid * 16);
  return wpair;
}

__device__ __forceinline__ void prep_weights(const Params& p, unsigned char* smem, uint32_t sb, int cta, int tid, int wid,
                                             uint32_t wpair, int tile0, int tile1, int& row_first, int& row_next LTPARAM) {
  float* sU = reinterpret_cast<float*>(smem + oU);
  float* sW5 = reinterpret_cast<float*>(smem + oW5);
  float* sM = reinterpret_cast<float*>(smem + oM);
  float* sC = reinterpret_cast<float*>(smem + oC);
  float* sL = reinterpret_cast<float*>(smem + oL);
  const int unit = max(cta - kUnit0, 0), step = unit / 7, part = unit % 7, col = min(cta, kF - 1);
  const bool is_w5 = tid < kSq / 2;
  const int ec = min(tid - kSq / 2, 3 * 13 - 1);
  *reinterpret_cast<float2*>(is_w5 ? sW5 + 2 * tid : sC + 2 * ec) =
      make_float2(__uint_as_float(wpair << 16), __uint_as_float(wpair & 0xffff0000u));
  LT(2);
  if (wid == 11) sts32(sb + kOffTag, read_launch_tag(p));
  if (tid == 0) init_barriers(sb);
  asm volatile("cp.async.wait_all;" ::: "memory");
  __syncthreads();
  LT(3);
  row_first = cin_row(p, tile0, tid & 31);
  row_next = cin_row(p, tile1, tid & 31);

  if (wid >= kHalf / 32) {
    unsigned char* dst = p.img + kSec0Bytes + step * kSecLBytes;
#pragma unroll 1
    for (int it = 0; it < 3; it++) {
      const int c = tid - kHalf + it * kHalf;
      if (cta >= kUnit0 && c < (part < 6 ? 13 * 32 : 8 * 32)) {
        const int rl = c >> 5, n = c & 31, i = min(n, kF - 1);
        const uint32_t src = oSl + i * (2 * kF);
        uint32_t e[4];
        if (part < 6) {
#pragma unroll
          for (int q = 0; q < 4; q++) {
            const uint32_t f = *reinterpret_cast<const unsigned short*>(smem + oTab + kTabPi + q * 28 + 2 * rl);
            const unsigned char* w = smem + src + q * kSlice + (part & 1) * 8;
            e[q] = *reinterpret_cast<const unsigned short*>(w + (f & 31) * 2) |
                   (uint32_t)*reinterpret_cast<const unsigned short*>(w + (f >> 8) * 2) << 16;
          }
        } else {
#pragma unroll
          for (int q = 0; q < 4; q++) {
            const uint32_t f = smem[oTab + kTabLin + rl * 4 + q];
            const unsigned char* w = smem + src + (f & 31) * 2;
            const uint32_t both = *reinterpret_cast<const unsigned short*>(w) |
                                  (uint32_t)*reinterpret_cast<const unsigned short*>(w + kSlice + 8) << 16;
            e[q] = (f >> 5) ? both : 0;
          }
          if (rl == 7) e[0] = reinterpret_cast<const unsigned short*>(smem + oWo)[(2 - step) * kF + i];
        }
        const int ri = 13 * part + rl;
        if (n >= kF) e[0] = e[1] = e[2] = e[3] = 0;
        *reinterpret_cast<uint4*>(dst + img_off(kZStep, ri >> 1, n, (ri & 1) * 8)) = make_uint4(e[0], e[1], e[2], e[3]);
      }
    }
  } else {
    const int t4 = min(tid, kSq / 4 - 1);
    float4 u = make_float4(0.f, 0.f, 0.f, 0.f);
#pragma unroll
    for (int h = 0; h < kF; h++) {
      const uint2 w = reinterpret_cast<const uint2*>(smem + oW6)[h * (kSq / 4) + t4];
      const float c = sC[2 * kF + h];
      u.x = fmaf(c, __uint_as_float(w.x << 16), u.x);
      u.y = fmaf(c, __uint_as_float(w.x & 0xffff0000u), u.y);
      u.z = fmaf(c, __uint_as_float(w.y << 16), u.z);
      u.w = fmaf(c, __uint_as_float(w.y & 0xffff0000u), u.w);
    }
    reinterpret_cast<float4*>(sU)[t4] = u;
    bar_sync(5, kHalf);
    {
      const int ap = min(tid / 14, 12), kp = tid % 14;
      const float* up = kp < 13 ? sU + 2 * kp : sC + kF;
      const int us = kp < 13 ? kF : 1;
      float m00 = 0.f, m01 = 0.f, m10 = 0.f, m11 = 0.f;
#pragma unroll
      for (int h = 0; h < kF; h++) {
        const float2 w = *reinterpret_cast<const float2*>(sW5 + h * kF + 2 * ap);
        const float u0 = up[h * us], u1 = up[h * us + 1];
        m00 = fmaf(w.x, u0, m00);
        m01 = fmaf(w.x, u1, m01);
        m10 = fmaf(w.y, u0, m10);
        m11 = fmaf(w.y, u1, m11);
      }
      if (kp < 13) {
        *reinterpret_cast<float2*>(sM + 2 * ap * kF + 2 * kp) = make_float2(m00, m01);
        *reinterpret_cast<float2*>(sM + (2 * ap + 1) * kF + 2 * kp) = make_float2(m10, m11);
      } else {
        *reinterpret_cast<float2*>(sL + 2 * ap) = make_float2(m00, m10);
      }
    }
    bar_sync(5, kHalf);
    static_assert(NK1 * 16 == 2 * kHalf, "two stage-1 features per thread");
    const unsigned short* sW1 = reinterpret_cast<const unsigned short*>(smem + oSl + 4 * kSlice + (col & 1) * 8);
    const uint32_t ff = reinterpret_cast<const uint32_t*>(smem + oTab)[tid];
    float gv[2], xv[2];
#pragma unroll
    for (int j = 0; j < 2; j++) {
      const int f = (ff >> (16 * j)) & 0xffff, a = f & 31, b = (f >> 5) & 31, bq = min(b, kF - 1), aq = min(a, kF - 1);
      const float g2 = sM[aq * kF + bq] + (a != b ? sM[bq * kF + aq] : 0.f);
      const float x2 = bf2f(sW1[aq * kF + bq]) + (a != b ? bf2f(sW1[bq * kF + aq]) : 0.f);
      gv[j] = (f >> 10) ? (b == kF ? (a == kF ? sC[col] : sL[aq]) : g2) : 0.f;
      xv[j] = ((f >> 10) && b != kF) ? x2 : 0.f;
    }
    if (cta < kF) {
      const uint32_t gb = pack_bf16(gv[0], gv[1]);
      const int nx = cta < 24 ? 32 + cta : cta, ng = cta < 24 ? cta : cta + 2;
      unsigned char* o = p.img + img_off(kS1Step, tid >> 3, 0, 2 * (tid & 7));
      *reinterpret_cast<uint32_t*>(o + img_off(0, 0, nx, 0)) = pack_bf16(xv[0], xv[1]);
      *reinterpret_cast<uint32_t*>(o + img_off(0, 0, ng, 0)) = gb;
    } else if (cta == kF) {
      *reinterpret_cast<uint4*>(p.img + img_off(kS1Step, tid >> 3, 28 + (tid & 3), 8 * ((tid >> 2) & 1))) = make_uint4(0, 0, 0, 0);
    }
  }
  LT(1);
  __syncthreads();
  LT(4);
  if (tid == 0) asm volatile("red.release.gpu.global.add.u32 [%0], 1;" ::"l"(p.prep_cnt) : "memory");
  LT(5);
}

__device__ __forceinline__ void load_section(const Params& p, uint32_t sb, int s) {
  const uint32_t bar = sb + kOffBar + (kBarW + s) * 8;
  const uint32_t bytes = s == 0 ? kSec0Bytes : kSecLBytes;
  mbar_expect_tx(bar, bytes);
  bulk_g2s(sb + s * kStageBytes, p.img + (s == 0 ? 0 : kSec0Bytes + (s - 1) * kSecLBytes), bytes, bar);
}

__device__ __forceinline__ void gemm_load_w(const CUtensorMap* wmap, uint32_t sb, int k, int n0, uint32_t rank) {
  const int s = k & 3;
  const uint32_t full = sb + kOffBar + (kBarFull + s) * 8;
  mbar_expect_tx(full, kBBytes);
  const uint32_t db = sb + s * kStageBytes + kABytes + rank * 16384;
  tma_2d_mc(db, wmap, n0 + rank * 128, k * 64, full, 3);
  tma_2d_mc(db + 8192, wmap, n0 + rank * 128 + 64, k * 64, full, 3);
}

__device__ __forceinline__ int2 ldg_early2(const int* p) {
  int2 v;
  asm volatile("ld.global.nc.v2.b32 {%0, %1}, [%2];" : "=r"(v.x), "=r"(v.y) : "l"(p));
  return v;
}

__device__ __forceinline__ void gemm_producer(const Params& p, const CUtensorMap* wmap, uint32_t sb, int t, int warp, int m0,
                                              int n0, uint32_t rank, int2* rows LTPARAM) {
  const int c = t & 7, r0 = t >> 3;
  const uint32_t dst0 = sb + r0 * 128 + ((c ^ (r0 & 7)) << 4);
  const int* ip = p.idx + (m0 + r0) * kF;
  const unsigned char* base = reinterpret_cast<const unsigned char*>(p.table) + c * 16;
  const bool issuer = warp == 0 && elect_one();
#pragma unroll 1
  for (int it = 0; it < kF / 2; it++) {
    const unsigned char* src[8];
#pragma unroll
    for (int s = 0; s < kStages; s++) {
      if ((s & 1) == 0) {
#pragma unroll
        for (int i = 0; i < 8; i++) src[i] = row_address(base, s == 0 ? rows[i].x : rows[i].y);
      }
      if (s == 2) {
        if (it + 1 < kF / 2) ip += 2;
#pragma unroll
        for (int i = 0; i < 8; i++) rows[i] = ldg_early2(ip + i * 16 * kF);
      }
      if (it > 0) mbar_wait(sb + kOffBar + (kBarEmpty + s) * 8, (it & 1) ^ 1);
      if ((it > 0 || s > 0) && issuer) gemm_load_w(wmap, sb, 4 * it + s, n0, rank);
#pragma unroll
      for (int i = 0; i < 8; i++) cp_async16_row(dst0 + s * kStageBytes + i * 2048, src[i] + (s & 1) * 128);
      if (s == 0 && it == 0) cluster_wait();
      cp_async_arrive(sb + kOffBar + (kBarFull + s) * 8);
      if (s == 0 && it == 0) LT(3);
      if (s == 3 && it == 0) LT(4);
    }
    if (it == 0) {
      build_tables(p, sb, t, true, n0);
      if (warp == 0) sts32(sb + kOffTag, read_launch_tag(p));
      fence_proxy_async_smem();
      bar_arrive(4, 256);
      bar_arrive(5, 256);
    }
  }
}

__device__ __forceinline__ void gemm_release(uint32_t sb, int k, int lane) {
  if (k < kKSteps - kStages) {
    if (lane < 2) mbar_arrive_cluster(sb + kOffBar + (kBarEmpty + (k & 3)) * 8, lane);
  } else if (lane == 0) {
    mbar_arrive(sb + kOffBar + (kBarDone + (k & 3)) * 8);
  }
}

template <int K>
__device__ __forceinline__ void dot_mma(float* d, const uint32_t* h, uint32_t desc) {
  if constexpr (K < 16) {
    wgmma_rs_n8<K * 16, K != 0>(d, h[4 * K], h[4 * K + 1], h[4 * K + 2], h[4 * K + 3], desc);
    dot_mma<K + 1>(d, h, desc);
  }
}

__device__ __forceinline__ void gemm_consumer(const Params& p, uint32_t sb, int wg, int warp, int lane, int m0, int nt,
                                              uint32_t xdst, int tile0, int row_first LTPARAM) {
  float acc[128];
  {
    const uint32_t* bp = reinterpret_cast<const uint32_t*>(p.b1 + nt * 256) + (lane & 3);
#pragma unroll
    for (int g = 0; g < 32; g++) {
      const uint32_t b2 = __ldg(bp + 4 * g);
      acc[4 * g] = acc[4 * g + 2] = __uint_as_float(b2 << 16);
      acc[4 * g + 1] = acc[4 * g + 3] = __uint_as_float(b2 & 0xffff0000u);
    }
    pin<128>(acc);
  }
  const uint64_t da0 = (uint64_t)(((sb + wg * 8192) & 0x3FFFF) >> 4) | ((uint64_t)1 << 16) | ((uint64_t)(1024 >> 4) << 32) | (1ull << 62);
  const uint64_t db0 = (uint64_t)(((sb + kABytes) & 0x3FFFF) >> 4) | ((uint64_t)(8192 >> 4) << 16) | ((uint64_t)(1024 >> 4) << 32) | (1ull << 62);
#define EXP_TAIL 3
  constexpr int kShared = kKSteps - EXP_TAIL;
  for (int k = 0; k < kShared; k++) {
    const int s = k & 3;
    mbar_wait(sb + kOffBar + (kBarFull + s) * 8, (k >> 2) & 1);
    fence_proxy_async_smem();
    if (k == 0) TS(2);
    if (k == 0) LT(4);
    const uint64_t so = (uint64_t)(s * (kStageBytes >> 4));
    wg_fence();
#pragma unroll
    for (int kk = 0; kk < 4; kk++) wgmma_ss_n256_tb(acc, da0 + so + kk * 2, db0 + so + kk * 128, 1);
    wg_commit();
    wg_wait<1>();
    if (k > 0) gemm_release(sb, k - 1, lane);
  }
  if (wg == 1) {
    wg_wait<0>();
    gemm_release(sb, kShared - 1, lane);
    bar_sync(6, 256);
  }
#pragma unroll
  for (int k = kShared; k < kKSteps; k++) {
    mbar_wait(sb + kOffBar + (kBarFull + (k & 3)) * 8, (k >> 2) & 1);
    fence_proxy_async_smem();
    const uint64_t so = (uint64_t)((k & 3) * (kStageBytes >> 4));
    wg_fence();
#pragma unroll
    for (int kk = 0; kk < 4; kk++) wgmma_ss_n256_tb(acc, da0 + so + kk * 2, db0 + so + kk * 128, 1);
    wg_commit();
    if (k == kKSteps - 1 && wg == 0) bar_arrive(6, 256);
    wg_wait<1>();
    if (k > kShared || wg == 0) gemm_release(sb, k - 1, lane);
  }
  wg_wait<0>();
  pin<128>(acc);
  gemm_release(sb, kKSteps - 1, lane);
  TS(3);
  LT(5);
  cin_issue(p, xdst, warp, tile0, row_first);
  if (wg == 0) bar_sync(4, 256); else bar_sync(5, 256);

  uint32_t hp[64];
#pragma unroll
  for (int j = 0; j < 64; j++) {
    float r[2];
#pragma unroll
    for (int e = 0; e < 2; e++) {
      const float x = acc[2 * j + e];
      r[e] = fmaf(x, tanh_fast(x * fmaf(x * x, 0.0356774081363001f, 0.7978845608028654f)), x);
    }
    hp[j] = pack_bf16(r[0], r[1]);
  }
  pin<64>(hp);
  float d[4];
  fence_proxy_async_smem();
  wg_fence();
  dot_mma<0>(d, hp, desc_plain(sb + kOffEpi));
  wg_commit();
  wg_wait<0>();
  pin<4>(d);
  if ((lane & 3) == 0) {
    const uint32_t tag = lds32(sb + kOffTag);
    unsigned long long* dst = p.dnn + nt * kB + m0 + wg * 64 + warp * 16 + (lane >> 2);
    st_tagged(dst, 0.5f * d[0], tag);
    st_tagged(dst + 8, 0.5f * d[2], tag);
  }
  __syncwarp();
}

__device__ __forceinline__ uint32_t s1_feature(const uint32_t* v, int ri, int row) {
  const int it = r_item(ri), ty = it & 3, s = (it >> 2) & 15, t = it >> 6;
  const uint32_t a = v[2 * s + row];
  return hmul2(ty == 0 ? dup_lo(a) : ty == 1 ? dup_hi(a) : a, v[2 * t + row]);
}
__device__ __forceinline__ uint32_t z_feature(const uint32_t* v, const uint32_t* gp, int ri, int row) {
  if (ri == 85) return hmul2(dup_lo(v[26 + row]), dup_lo(v[26 + row]));
  if (ri >= 78) {
    const uint32_t a = v[2 * (tail_pos(ri - 78) >> 1) + row];
    return hmul2((tail_pos(ri - 78) & 1) ? dup_hi(a) : dup_lo(a), gp[6 + row]);
  }
  const int u = ri / 13;
  const uint32_t a = gp[2 * (u >> 1) + row];
  return hmul2((u & 1) ? dup_hi(a) : dup_lo(a), v[2 * (ri % 13) + row]);
}
#define EXP_SBT 2
#define EXP_SNB 2
#define EXP_ZBT 1
#define EXP_ZNB 6
template <int K, int KEND, int BT>
__device__ __forceinline__ void s1_mma(float* a1, const uint32_t* f, uint32_t d) {
  if constexpr (K < KEND) {
    wgmma_rs_n56<K * (kS1Step >> 4), K != 0>(a1, f[0], f[1], f[2], f[3], d);
    if constexpr ((K + 1) % BT != 0) s1_mma<K + 1, KEND, BT>(a1, f + 4, d);
  }
}
template <int B, int BT, int NB>
__device__ __forceinline__ void s1_batches(float* a1, const uint32_t* v, uint32_t* fr, uint32_t d) {
  if constexpr (B * BT < NK1) {
    constexpr int nk = (NK1 - B * BT) < BT ? (NK1 - B * BT) : BT;
    uint32_t* f = fr + (B % NB) * 4 * BT;
    if (B >= NB) wg_wait<NB - 1>();
#pragma unroll
    for (int j = 0; j < 4 * nk; j++) f[j] = s1_feature(v, 2 * (B * BT + (j >> 2)) + ((j >> 1) & 1), j & 1);
    pin<4 * nk>(f);
    wg_fence();
    s1_mma<B * BT, NK1, BT>(a1, f, d);
    wg_commit();
    s1_batches<B + 1, BT, NB>(a1, v, fr, d);
  }
}
template <int K, int KEND, int BT>
__device__ __forceinline__ void z_mma(float* y, const uint32_t* f, uint32_t d) {
  if constexpr (K < KEND) {
    wgmma_rs_n32<K * (kZStep >> 4), K != 0>(y, f[0], f[1], f[2], f[3], d);
    if constexpr ((K + 1) % BT != 0) z_mma<K + 1, KEND, BT>(y, f + 4, d);
  }
}
template <int B, int BT, int NB>
__device__ __forceinline__ void z_batches(float* y, const uint32_t* v, const uint32_t* gp, uint32_t* fr, uint32_t d) {
  if constexpr (B * BT < kNKZ) {
    constexpr int nk = (kNKZ - B * BT) < BT ? (kNKZ - B * BT) : BT;
    uint32_t* f = fr + (B % NB) * 4 * BT;
    if (B >= NB) wg_wait<NB - 1>();
#pragma unroll
    for (int j = 0; j < 4 * nk; j++) f[j] = z_feature(v, gp, 2 * (B * BT + (j >> 2)) + ((j >> 1) & 1), j & 1);
    pin<4 * nk>(f);
    wg_fence();
    z_mma<B * BT, kNKZ, BT>(y, f, d);
    wg_commit();
    z_batches<B + 1, BT, NB>(y, v, gp, fr, d);
  }
}

__device__ __forceinline__ void cin_tiles(const Params& p, uint32_t sb, int wg, int warp, int lane, int tile, int next,
                                          int tile_begin, int tile_end, bool head, bool tail, int split, int row_next,
                                          uint32_t xdst) {
  uint4* state = p.state + split * (12 * 128) + warp * 32 + lane;
  const int last = tail ? kPlain + kSplit + split : kTiles;
  const uint32_t xbase = sb + kOffX + wg * kXBytes + warp * 32;
  bool first = true;
  mbar_wait(sb + kOffBar + kBarW * 8, 0);
  uint32_t xa[7];
  {
    const uint4 o0 = lds128u(sb + kOffLd + lane * 32), o1 = lds128u(sb + kOffLd + lane * 32 + 16);
    xa[0] = xbase + o0.x; xa[1] = xbase + o0.y; xa[2] = xbase + o0.z; xa[3] = xbase + o0.w;
    xa[4] = xbase + o1.x; xa[5] = xbase + o1.y; xa[6] = xbase + o1.z;
  }
  const uint32_t d1 = desc_plain(sb);
  uint32_t v[28], fr[48], gp[8];
  float y[16];
  auto load_v = [&]() {
    asm volatile("cp.async.wait_group 0;" ::: "memory");
    __syncwarp();
#pragma unroll
    for (int c = 0; c < 7; c++) ldsm4t(v + 4 * c, xa[c]);
  };
  auto layers = [&](int l, bool stop) {
#pragma unroll 1
    for (;; l++) {
      if (first) mbar_wait(sb + kOffBar + (kBarW + l) * 8, 0);
      z_batches<0, EXP_ZBT, EXP_ZNB>(y, v, gp, fr, desc_plain(sb + l * kStageBytes));
      wg_wait<0>();
      pin<16>(y);
      if (l == 3) break;
#pragma unroll
      for (int j = 0; j < 8; j++) gp[j] = pack_bf16(y[2 * j], y[2 * j + 1]);
      gp[6] = __shfl_sync(0xffffffffu, gp[6], 0, 4);
      gp[7] = __shfl_sync(0xffffffffu, gp[7], 0, 4);
      if (stop && l == kHeadLayers) break;
    }
  };
  auto finish = [&](const float* x) {
    float s0 = 0.f, s1 = 0.f;
#pragma unroll
    for (int j = 0; j < 16; j += 2) {
      s0 = fmaf(x[(j + 4) & 15], y[j], s0);
      s1 = fmaf(x[(j + 5) & 15], y[j + 1], s1);
    }
    float s = s0 + s1;
#pragma unroll
    for (int o = 16; o > 0; o >>= 1) s += __shfl_xor_sync(0xffffffffu, s, o);
    if (lane == 0) {
      const bool sibling = tile >= kPlain && tile < kPlain + kSplit;
      if (sibling || (tile == tile_begin && (tile & 1)))
        st_tagged((sibling ? p.pool + (tile - kPlain) * 4 : p.half + blockIdx.x * 4) + warp, s, lds32(sb + kOffTag));
      else
        sts32(sb + kOffPart + (min(tile - tile_begin, kMaxTiles - 1) * 4 + warp) * 4, __float_as_uint(s));
    }
  };
  while (head || tile < tile_end) {
    TS(8 + min((tile_end - tile - 1) / 3, 15));
    load_v();
    float a1[28];
    s1_batches<0, EXP_SBT, EXP_SNB>(a1, v, fr, d1);
    wg_wait<0>();
    pin<28>(a1);
    cin_issue(p, xdst, warp, next < tile_end ? next : last, row_next);
    row_next = cin_row(p, next + 3 < tile_end ? next + 3 : last, lane);
#pragma unroll
    for (int j = 0; j < 8; j++) gp[j] = pack_bf16(a1[2 * j], a1[2 * j + 1]);
    gp[6] = __shfl_sync(0xffffffffu, gp[6], 1, 4);
    gp[7] = __shfl_sync(0xffffffffu, gp[7], 1, 4);
    layers(1, head);
    if (head) {
      const uint32_t tag = lds32(sb + kOffTag);
#pragma unroll
      for (int j = 0; j < 12; j++)
        st_relaxed128(state + j * 128, j < 4 ? gp[2 * j] : __float_as_uint(a1[2 * j + 4]), tag,
                      j < 4 ? gp[2 * j + 1] : __float_as_uint(a1[2 * j + 5]), tag);
      head = false;
    } else {
      first = false;
      finish(a1 + 12);
    }
    tile = next;
    next += 3;
  }
  if (tail) {
    tile = last;
    load_v();
    float x[16];
    const uint32_t tag = lds32(sb + kOffTag);
    uint32_t spins = 0;
    bool ok;
    do {
      ok = true;
#pragma unroll
      for (int j = 0; j < 12; j++) {
        const uint4 w = ld_relaxed128(state + j * 128);
        ok = ok && w.y == tag && w.w == tag;
        if (j < 4) { gp[2 * j] = w.x; gp[2 * j + 1] = w.z; }
        else { x[2 * j - 8] = __uint_as_float(w.x); x[2 * j - 7] = __uint_as_float(w.z); }
      }
      if (++spins > kSpinLimit) __trap();
    } while (!__all_sync(0xffffffffu, ok));
    layers(kHeadLayers + 1, false);
    finish(x);
  }
}

__global__ void __cluster_dims__(2, 1, 1) __launch_bounds__(kThreads, 1)
xdeepfm_kernel(const __grid_constant__ CUtensorMap wmap, const Params p) {
  extern __shared__ __align__(1024) unsigned char smem[];
  LT(0);
  const int tid = threadIdx.x, lane = tid & 31;
  const int cta = blockIdx.x;
  const bool is_gemm = cta >= kPrepCtas;
  const int g = cta - kPrepCtas;
  const int m0 = (((g >> 1) / 13) * 2 + (g & 1)) * 128;
  const uint32_t sb = (uint32_t)__cvta_generic_to_shared(smem);
  int2 rows[8];
  if (!is_gemm) {
    rows[0].x = (int)prep_issue(p, sb, cta, tid);
  } else if (tid >= 256) {
    const int* ip = p.idx + (m0 + ((tid - 256) >> 3)) * kF;
#pragma unroll
    for (int i = 0; i < 8; i++) rows[i] = ldg_early2(ip + i * 16 * kF);
  }
  const int n0 = ((g >> 1) % 13) * 256;
  if (is_gemm && tid == 0) init_barriers(sb);
  __syncwarp();
  if (is_gemm) cluster_arrive();
  const int wg = __shfl_sync(0xffffffffu, tid >> 7, 0);
  const int warp = __shfl_sync(0xffffffffu, (tid >> 5) & 3, 0);
  TS(0);

  int tile_begin, tile_end;
  if (is_gemm) {
    tile_begin = kTilesPrep + g * kBaseTiles;
    tile_end = tile_begin + kBaseTiles;
  } else {
    tile_begin = cta * kTilesPrep / kPrepCtas;
    tile_end = (cta + 1) * kTilesPrep / kPrepCtas;
  }
  int split = cta + wg * kPrepCtas;
  const bool head = !is_gemm && wg < 2 && split < kSplit;
  bool tail = false;
  const int own0 = tile_begin + (wg + 1) % 3;
  const int tile0 = head ? kPlain + kSplit + split : own0, tile1 = head ? own0 : own0 + 3;
  const uint32_t xdst = sb + kOffX + wg * kXBytes + min(lane, kF - 1) * kXPitch + warp * 32;
  int row_first, row_next;
  LT(1);
  if (is_gemm) {
    TS(1);
    LT(2);
    row_first = cin_row(p, tile0, lane);
    row_next = cin_row(p, tile1, lane);
    if (wg == 2) {
      gemm_producer(p, &wmap, sb, tid - 256, warp, m0, n0, (uint32_t)(g & 1), rows LTARG);
      cin_issue(p, xdst, warp, tile0, row_first);
      if (tid == 256) {
        const uint32_t tag = lds32(sb + kOffTag);
        sts32(sb + kOffTicket, atomicAdd(p.ticket, 1u) - (tag - 1) * kGemmCtas);
        wait_prep(p, tag);
        fence_proxy_async();
        for (int s = 0; s < kStages; s++) {
          mbar_wait(sb + kOffBar + (kBarDone + s) * 8, 0);
          load_section(p, sb, s);
        }
      }
      bar_sync(3, 128);
      split = __shfl_sync(0xffffffffu, lds32(sb + kOffTicket), 0);
      tail = split < kSplit;
    } else {
      cluster_wait();
      if (tid == 0) gemm_load_w(&wmap, sb, 0, n0, (uint32_t)(g & 1));
      __syncwarp();
      LT(3);
      gemm_consumer(p, sb, wg, warp, lane, m0, (g >> 1) % 13, xdst, tile0, row_first LTARG);
    }
  } else
  {
    prep_weights(p, smem, sb, cta, tid, wg * 4 + warp, (uint32_t)rows[0].x, tile0, tile1, row_first, row_next LTARG);
    TS(1);
    cin_issue(p, xdst, warp, tile0, row_first);
    if (wg == 2) {
      build_tables(p, sb, tid - 256, false, 0);
    } else if (tid == 0) {
      wait_prep(p, lds32(sb + kOffTag));
      fence_proxy_async();
      for (int s = 0; s < kStages; s++) load_section(p, sb, s);
    }
    __syncthreads();
  }

  TS(4);
  LT(6);
  cin_tiles(p, sb, wg, warp, lane, tile0, tile1, tile_begin, tile_end, head, tail, min(split, kSplit - 1), row_next, xdst);
  TS(6);
  LT(7);

  uint32_t order = 0;
  if (lane == 0) {
    asm volatile("atom.shared.add.u32 %0, [%1], 1;" : "=r"(order) : "r"(sb + kOffMisc) : "memory");
    mbar_arrive(sb + kOffBar + kBarFin * 8);
  }
  if (__shfl_sync(0xffffffffu, order, 0) == 0) {
    const int plain_end = min(tile_end, kPlain);
    const int b0 = (tile_begin + 1) >> 1, nb = ((plain_end + 1) >> 1) - b0;
    const uint32_t tag = lds32(sb + kOffTag);
    const uint32_t drawn = is_gemm ? lds32(sb + kOffTicket) : kSplit;
    const bool pooled = lane == 31 && drawn < kSplit;
    const int row = pooled ? kPlainRows + drawn : b0 + lane;
    float t = 0.f;
    if (lane < nb || pooled) {
      t = bf2f(__ldg(p.bout));
      t += sum_tagged<13>(p.dnn + row, kB, tag);
      if (pooled || 2 * row + 1 == tile_end) t += sum_tagged<4>(pooled ? p.pool + drawn * 4 : p.half + (cta + 1) * 4, 1, tag);
    }
    __syncwarp();
    mbar_wait_idle(sb + kOffBar + kBarFin * 8, 0);
    if (lane < nb || pooled) {
      const int t0 = pooled ? kMaxTiles - 1 : 2 * row - tile_begin;
      const float4 a = lds128f(sb + kOffPart + t0 * 16);
      t += (a.x + a.y) + (a.z + a.w);
      if (!pooled && 2 * row + 1 < tile_end) {
        const float4 c = lds128f(sb + kOffPart + t0 * 16 + 16);
        t += (c.x + c.y) + (c.z + c.w);
      }
      p.out[row] = f2bf(t);
    }
    if (lane == 0) atomicAdd(p.exit_cnt, 1ull);
    TS(7);
  }
  asm volatile("cp.async.wait_group 0;" ::: "memory");
}

__global__ void __launch_bounds__(256) xdeepfm_fallback(const Params p, const unsigned short* w1) {
  __shared__ float x0[kDin], xa[kDin], xb[kDin], red[8];
  const int b = blockIdx.x, tid = threadIdx.x;
  for (int i = tid; i < kDin; i += 256) xa[i] = x0[i] = bf2f(p.table[(size_t)p.idx[b * kF + i / kD] * kD + i % kD]);
  __syncthreads();
  float s = 0.f;
  float *cur = xa, *nxt = xb;
  for (int l = 0; l < 6; l++) {
    for (int o = tid; o < kDin; o += 256) {
      const int h = o / kD, d = o % kD;
      float a = 0.f;
      for (int i = 0; i < kF; i++) {
        float t = 0.f;
        for (int j = 0; j < kF; j++) t = fmaf(bf2f(p.ws[((l * kF + h) * kF + i) * kF + j]), x0[j * kD + d], t);
        a = fmaf(t, cur[i * kD + d], a);
      }
      nxt[o] = a;
      s = fmaf(a, bf2f(p.wout[l * kF + h]), s);
    }
    __syncthreads();
    float* t = cur; cur = nxt; nxt = t;
  }
  for (int n = tid; n < kDin; n += 256) {
    float a = bf2f(p.b1[n]);
    for (int k = 0; k < kDin; k++) a = fmaf(x0[k], bf2f(w1[(size_t)k * kDin + n]), a);
    s = fmaf(0.5f * a * (1.f + tanhf(0.7978845608028654f * (a + 0.044715f * a * a * a))), bf2f(p.w2[n]), s);
  }
  for (int o = 16; o > 0; o >>= 1) s += __shfl_xor_sync(0xffffffffu, s, o);
  if ((tid & 31) == 0) red[tid >> 5] = s;
  __syncthreads();
  if (tid == 0) {
    float t = bf2f(p.bout[0]);
    for (int i = 0; i < 8; i++) t += red[i];
    p.out[b] = f2bf(t);
  }
}

typedef CUresult (*EncodeFn)(CUtensorMap*, CUtensorMapDataType, cuuint32_t, void*, const cuuint64_t*, const cuuint64_t*,
                             const cuuint32_t*, const cuuint32_t*, CUtensorMapInterleave, CUtensorMapSwizzle,
                             CUtensorMapL2promotion, CUtensorMapFloatOOBfill);

}

extern "C" void kernel_launch(void* const* d_in, const int* in_sizes, int n_in, void* d_out, int out_size) {
  (void)in_sizes; (void)n_in; (void)out_size;
  static EncodeFn encode = nullptr;
  static bool resident = false;
  static Params sym;
  if (!encode) {
    void* fn = nullptr;
    cudaDriverEntryPointQueryResult qr;
    cudaGetDriverEntryPoint("cuTensorMapEncodeTiled", &fn, cudaEnableDefault, &qr);
    encode = (EncodeFn)fn;
    cudaFuncSetAttribute(xdeepfm_kernel, cudaFuncAttributeMaxDynamicSharedMemorySize, kSmemBytes);
    cudaGetSymbolAddress((void**)&sym.tab, c_tab);
    cudaGetSymbolAddress((void**)&sym.img, g_img);
    cudaGetSymbolAddress((void**)&sym.dnn, g_dnn);
    cudaGetSymbolAddress((void**)&sym.half, g_half);
    cudaGetSymbolAddress((void**)&sym.pool, g_pool);
    cudaGetSymbolAddress((void**)&sym.state, g_state);
    cudaGetSymbolAddress((void**)&sym.ticket, g_ticket);
    cudaGetSymbolAddress((void**)&sym.exit_cnt, g_exit_cnt);
    cudaGetSymbolAddress((void**)&sym.prep_cnt, g_prep_cnt);
    cudaLaunchConfig_t cfg = {};
    cfg.gridDim = dim3(kCtas);
    cfg.blockDim = dim3(kThreads);
    cfg.dynamicSmemBytes = kSmemBytes;
    cudaLaunchAttribute at;
    at.id = cudaLaunchAttributeClusterDimension;
    at.val.clusterDim.x = 2;
    at.val.clusterDim.y = 1;
    at.val.clusterDim.z = 1;
    cfg.attrs = &at;
    cfg.numAttrs = 1;
    int clusters = 0;
    resident = cudaOccupancyMaxActiveClusters(&clusters, xdeepfm_kernel, &cfg) == cudaSuccess && 2 * clusters >= kCtas;
  }
  CUtensorMap wmap;
  const cuuint64_t dims[2] = {(cuuint64_t)kDin, (cuuint64_t)kDin};
  const cuuint64_t strides[1] = {(cuuint64_t)kDin * 2};
  const cuuint32_t box[2] = {64, 64};
  const cuuint32_t es[2] = {1, 1};
  encode(&wmap, CU_TENSOR_MAP_DATA_TYPE_BFLOAT16, 2, d_in[4], dims, strides, box, es, CU_TENSOR_MAP_INTERLEAVE_NONE,
         CU_TENSOR_MAP_SWIZZLE_128B, CU_TENSOR_MAP_L2_PROMOTION_L2_256B, CU_TENSOR_MAP_FLOAT_OOB_FILL_NONE);
  Params p = sym;
  p.idx = (const int*)d_in[0];
  p.table = (const unsigned short*)d_in[1];
  p.ws = (const unsigned short*)d_in[2];
  p.wout = (const unsigned short*)d_in[3];
  p.b1 = (const unsigned short*)d_in[5];
  p.w2 = (const unsigned short*)d_in[6];
  p.bout = (const unsigned short*)d_in[7];
  p.out = (unsigned short*)d_out;
  if (resident) xdeepfm_kernel<<<kCtas, kThreads, kSmemBytes>>>(wmap, p);
  else xdeepfm_fallback<<<kB, 256>>>(p, (const unsigned short*)d_in[4]);
}
```
